```python
import torch

def _softmax(x, axis=-1):
    return torch.softmax(x, dim=axis)
def _gelu(x):
    return torch.nn.functional.gelu(x, approximate="tanh")
def _silu(x):
    return torch.nn.functional.silu(x)
def _sigmoid(x):
    return torch.sigmoid(x)
def _layernorm(x, axis=-1, eps=1e-5):
    m = x.mean(dim=axis, keepdim=True)
    v = x.var(dim=axis, keepdim=True, unbiased=False)
    return (x - m) / torch.sqrt(v + eps)
def _scatter_add(tgt, idx, src, axis=0):
    return tgt.clone().index_add_(axis, idx, src)
def _segment_sum(src, seg, n):
    out = torch.zeros((n,) + src.shape[1:], dtype=src.dtype)
    return out.index_add_(0, seg, src)
def _pad(x, pw):
    flat = tuple(v for pair in reversed(pw) for v in pair)
    return torch.nn.functional.pad(x, flat)

kernel_name = 'sequential_preLN__mha_block__mixer_s_mlp__prompt'

def setup_inputs():

    _w = (lambda a: (lambda t: t.to(torch.bfloat16) if t.is_floating_point() else t)(torch.as_tensor(a)))
    def _A_setup():
        B, S, D, H = 1, 2048, 576, 32
        return {
            "x": _w((lambda *s: torch.randn(*s, dtype=torch.bfloat16) * 0.05)(B, S, D)),
            "wqkv": _w((lambda *s: torch.randn(*s, dtype=torch.bfloat16) * 0.05)(D, 3 * D)),
            "wo": _w((lambda *s: torch.randn(*s, dtype=torch.bfloat16) * 0.05)(D, D)),
        }
    _A_in = _A_setup()

    def _B_setup():
        B, S, D, F = 1, 2048, 576, 4608
        return {
            "x":  _w((lambda *s: torch.randn(*s, dtype=torch.bfloat16) * 0.05)(B, S, D)),
            "w1": _w((lambda *s: torch.randn(*s, dtype=torch.bfloat16) * 3.2)(D, D) * (D ** -0.5)),
            "w2": _w((lambda *s: torch.randn(*s, dtype=torch.bfloat16) * 3.2)(D, D) * (D ** -0.5)),
            "w3": _w((lambda *s: torch.randn(*s, dtype=torch.bfloat16) * 3.2)(D, F) * (D ** -0.5)),
            "w4": _w((lambda *s: torch.randn(*s, dtype=torch.bfloat16) * 3.2)(F, D) * (F ** -0.5)),
        }
    _B_in = _B_setup()

    return {
        "A_x": _A_in["x"],
        "A_wqkv": _A_in["wqkv"],
        "A_wo": _A_in["wo"],
        "B_x": _B_in["x"],
        "B_w1": _B_in["w1"],
        "B_w2": _B_in["w2"],
        "B_w3": _B_in["w3"],
        "B_w4": _B_in["w4"],
    }

def reference(A_x, A_wqkv, A_wo, B_x, B_w1, B_w2, B_w3, B_w4):
    def _A_ref(x, wqkv, wo):
        B, S, D = x.shape
        H = 32
        Dh = D // H
        qkv = (lambda x, *d: x.permute(*d))((x @ wqkv).reshape(B, S, 3, H, Dh), 2, 0, 3, 1, 4)
        q, k, v = qkv[0], qkv[1], qkv[2]
        scores = torch.einsum("bhqd,bhkd->bhqk", q, k) * (Dh ** -0.5)
        p = _softmax(scores, axis=-1)
        o = torch.einsum("bhqk,bhkd->bhqd", p, v)
        return (lambda x, *d: x.permute(*d))(o, 0, 2, 1, 3).reshape(B, S, D) @ wo

    def _B_ref(x, w1, w2, w3, w4):
        B, S, D = x.shape
        h = _gelu(_layernorm(x, axis=-1) @ w1)
        c = D // 4
        g0 = _pad(h[:, :, 0*c:1*c], ((0, 0), (1, 0), (0, 0)))[:, :S, :]
        g1 = _pad(h[:, :, 1*c:2*c], ((0, 0), (0, 1), (0, 0)))[:, 1:, :]
        g2 = _pad(h[:, :, 2*c:3*c], ((0, 0), (2, 0), (0, 0)))[:, :S, :]
        g3 = _pad(h[:, :, 3*c:   ], ((0, 0), (0, 2), (0, 0)))[:, 2:, :]
        hs = torch.concatenate([g0, g1, g2, g3], axis=-1) @ w2
        x1 = x + hs
        h2 = _gelu(_layernorm(x1, axis=-1) @ w3) @ w4
        return x1 + h2

    x = A_x
    h = x + _A_ref(_layernorm(x, axis=-1), A_wqkv, A_wo)
    h2 = h + _B_ref(_layernorm(h, axis=-1), B_w1, B_w2, B_w3, B_w4)
    return h2
```

```cpp
#include <cuda_runtime.h>
#include <cuda_bf16.h>
#include <cuda.h>
#include <stdint.h>

typedef __nv_bfloat16 bf16;
constexpr int S_ = 2048, D_ = 576, NH_ = 32, F_ = 4608;
constexpr float LN_EPS = 1e-5f;
constexpr int SPIN_MAX = 1 << 18;

#define POLY_MASK 0x6186

__device__ __align__(1024) bf16 g_qkv[3 * NH_ * S_ * 24];
__device__ float g_kmax2[NH_ * 256];
__device__ __align__(1024) bf16 g_o[S_ * D_];
__device__ __align__(1024) bf16 g_h[S_ * D_];
__device__ __align__(1024) bf16 g_gs[(S_ + 4) * D_];
__device__ __align__(1024) bf16 g_x1[S_ * D_];
__device__ __align__(16) float2 g_st_x[S_];
__device__ __align__(16) float g_csq[16 * 1728];
__device__ __align__(16) float2 g_st_h[S_ * 8];
__device__ __align__(16) float2 g_st_x1[S_ * 8];
__device__ __align__(1024) bf16 g_wimg[3 * D_ * D_];
__device__ unsigned g_cm[64];
__device__ float g_cs1[D_];
__device__ float g_cs3[F_];

extern __shared__ __align__(1024) uint8_t dsm[];

__device__ __forceinline__ uint32_t s2u(const void* p) { return (uint32_t)__cvta_generic_to_shared(p); }
__device__ __forceinline__ void mb_init(uint32_t b, int c) { asm volatile("mbarrier.init.shared::cta.b64 [%0], %1;" ::"r"(b), "r"(c) : "memory"); }
__device__ __forceinline__ void mb_expect(uint32_t b, int bytes) { asm volatile("mbarrier.arrive.expect_tx.shared::cta.b64 _, [%0], %1;" ::"r"(b), "r"(bytes) : "memory"); }
__device__ __forceinline__ void mb_arrive(uint32_t b) { asm volatile("mbarrier.arrive.shared::cta.b64 _, [%0];" ::"r"(b) : "memory"); }
__device__ __forceinline__ void mb_arrive_cl(uint32_t b, uint32_t cta) {
  asm volatile("{\n.reg .b32 r;\nmapa.shared::cluster.u32 r, %0, %1;\nmbarrier.arrive.shared::cluster.b64 _, [r];\n}" ::"r"(b), "r"(cta) : "memory");
}
__device__ __forceinline__ void mb_wait(uint32_t b, uint32_t ph) {
  asm volatile("{\n.reg .pred p;\n.reg .u32 n;\nmbarrier.try_wait.parity.shared::cta.b64 p, [%0], %1;\n@p bra DN;\nmov.u32 n, 0;\n"
               "LP: mbarrier.try_wait.parity.shared::cta.b64 p, [%0], %1;\nadd.u32 n, n, 1;\n@p bra DN;\nsetp.lt.u32 p, n, %2;\n@p bra LP;\nDN:\n}" ::"r"(b), "r"(ph), "n"(SPIN_MAX) : "memory");
}
__device__ __forceinline__ void fence_mb_init() { asm volatile("fence.mbarrier_init.release.cluster;" ::: "memory"); }
__device__ __forceinline__ void fence_async() { asm volatile("fence.proxy.async.shared::cta;" ::: "memory"); }
__device__ __forceinline__ void tma2d(uint32_t dst, const CUtensorMap* m, int x, int y, uint32_t b) {
  asm volatile("cp.async.bulk.tensor.2d.shared::cluster.global.mbarrier::complete_tx::bytes [%0], [%1, {%3, %4}], [%2];" ::"r"(dst), "l"(m), "r"(b), "r"(x), "r"(y) : "memory");
}
__device__ __forceinline__ void tma3d(uint32_t dst, const CUtensorMap* m, int x, int y, int z, uint32_t b) {
  asm volatile("cp.async.bulk.tensor.3d.shared::cluster.global.mbarrier::complete_tx::bytes [%0], [%1, {%3, %4, %5}], [%2];" ::"r"(dst), "l"(m), "r"(b), "r"(x), "r"(y), "r"(z) : "memory");
}
__device__ __forceinline__ void tma2d_mc(uint32_t dst, const CUtensorMap* m, int x, int y, uint32_t b, uint16_t mask) {
  asm volatile("cp.async.bulk.tensor.2d.shared::cluster.global.mbarrier::complete_tx::bytes.multicast::cluster [%0], [%1, {%3, %4}], [%2], %5;" ::"r"(dst), "l"(m), "r"(b), "r"(x), "r"(y), "h"(mask) : "memory");
}
__device__ __forceinline__ void bulk_g2s(uint32_t dst, const void* src, int bytes, uint32_t b) {
  asm volatile("cp.async.bulk.shared::cluster.global.mbarrier::complete_tx::bytes [%0], [%1], %2, [%3];" ::"r"(dst), "l"(src), "r"(bytes), "r"(b) : "memory");
}
__device__ __forceinline__ void bulk_g2s_mc(uint32_t dst, const void* src, int bytes, uint32_t b, uint16_t mask) {
  asm volatile("cp.async.bulk.shared::cluster.global.mbarrier::complete_tx::bytes.multicast::cluster [%0], [%1], %2, [%3], %4;" ::"r"(dst), "l"(src), "r"(bytes), "r"(b), "h"(mask) : "memory");
}
__device__ __forceinline__ void tma2d_st(const CUtensorMap* m, int x, int y, uint32_t src) {
  asm volatile("cp.async.bulk.tensor.2d.global.shared::cta.bulk_group [%0, {%2, %3}], [%1];" ::"l"(m), "r"(src), "r"(x), "r"(y) : "memory");
}
__device__ __forceinline__ void bulk_s2g(void* dst, uint32_t src, int bytes) {
  asm volatile("cp.async.bulk.global.shared::cta.bulk_group [%0], [%1], %2;" ::"l"(dst), "r"(src), "r"(bytes) : "memory");
}
__device__ __forceinline__ void tma2d_red_add(const CUtensorMap* m, int x, int y, uint32_t src) {
  asm volatile("cp.reduce.async.bulk.tensor.2d.global.shared::cta.add.bulk_group [%0, {%2, %3}], [%1];" ::"l"(m), "r"(src), "r"(x), "r"(y) : "memory");
}
__device__ __forceinline__ void bulk_commit() { asm volatile("cp.async.bulk.commit_group;" ::: "memory"); }
template <int N> __device__ __forceinline__ void bulk_wait_read() { asm volatile("cp.async.bulk.wait_group.read %0;" ::"n"(N) : "memory"); }
template <int N> __device__ __forceinline__ void bulk_wait() { asm volatile("cp.async.bulk.wait_group %0;" ::"n"(N) : "memory"); }
__device__ __forceinline__ void prefetch_l2(const void* p, int bytes) { asm volatile("cp.async.bulk.prefetch.L2.global [%0], %1;" ::"l"(p), "r"(bytes) : "memory"); }
__device__ __forceinline__ void prefetch_map(const CUtensorMap* m) { asm volatile("prefetch.tensormap [%0];" ::"l"(m) : "memory"); }
__device__ __forceinline__ void pdl_wait() { asm volatile("griddepcontrol.wait;" ::: "memory"); }
__device__ __forceinline__ void pdl_launch() { asm volatile("griddepcontrol.launch_dependents;" ::: "memory"); }
__device__ __forceinline__ void wg_fence() { asm volatile("wgmma.fence.sync.aligned;" ::: "memory"); }
__device__ __forceinline__ void wg_commit() { asm volatile("wgmma.commit_group.sync.aligned;" ::: "memory"); }
template <int N> __device__ __forceinline__ void wg_wait() { asm volatile("wgmma.wait_group.sync.aligned %0;" ::"n"(N) : "memory"); }
template <int N> __device__ __forceinline__ void reg_fence(float (&d)[N]) {
#pragma unroll
  for (int i = 0; i < N; i++) asm volatile("" : "+f"(d[i])::"memory");
}
__device__ __forceinline__ void sched_fence(uint32_t z) { asm volatile("{\n.reg .pred p;\nsetp.ne.u32 p, %0, 0;\nSF: @p nanosleep.u32 32;\n@p bra SF;\n}" ::"r"(z) : "memory"); }
template <int N> __device__ __forceinline__ void reg_dec() { asm volatile("setmaxnreg.dec.sync.aligned.u32 %0;" ::"n"(N)); }
template <int N> __device__ __forceinline__ void reg_inc() { asm volatile("setmaxnreg.inc.sync.aligned.u32 %0;" ::"n"(N)); }
__device__ __forceinline__ void bar_sync(int id, int n) { asm volatile("bar.sync %0, %1;" ::"r"(id), "r"(n) : "memory"); }
__device__ __forceinline__ void cluster_sync() { asm volatile("barrier.cluster.arrive.relaxed.aligned;\nbarrier.cluster.wait.aligned;" ::: "memory"); }
__device__ __forceinline__ uint64_t mkdesc(uint32_t addr, uint32_t lbo, uint32_t sbo, uint32_t sw) {
  return (uint64_t)((addr >> 4) & 0x3FFF) | ((uint64_t)(lbo >> 4) << 16) | ((uint64_t)(sbo >> 4) << 32) | ((uint64_t)sw << 62);
}
__device__ __forceinline__ void sts32(uint32_t a, uint32_t v) { asm volatile("st.shared.b32 [%0], %1;" ::"r"(a), "r"(v) : "memory"); }
__device__ __forceinline__ uint32_t pack2(float lo, float hi) { uint32_t r; asm("cvt.rn.bf16x2.f32 %0, %1, %2;" : "=r"(r) : "f"(hi), "f"(lo)); return r; }
__device__ __forceinline__ float blo(uint32_t w) { return __uint_as_float(w << 16); }
__device__ __forceinline__ float bhi(uint32_t w) { return __uint_as_float(w & 0xffff0000u); }
__device__ __forceinline__ float ex2(float x) { float r; asm("ex2.approx.ftz.f32 %0, %1;" : "=f"(r) : "f"(x)); return r; }
__device__ __forceinline__ float tanh_fast(float x) { float r; asm("tanh.approx.f32 %0, %1;" : "=f"(r) : "f"(x)); return r; }
__device__ __forceinline__ float gelu_s(float t, float ca, float cb, float ch) {
  float p = fmaf(t * t, cb, ca);
  float th = tanh_fast(t * p);
  float hu = t * ch;
  return fmaf(hu, th, hu);
}
constexpr float GELU_C0 = 0.7978845608028654f, GELU_C1 = 0.7978845608028654f * 0.044715f;
__device__ __forceinline__ float nz(float v) { return __float_as_uint(v) == 0u ? -0.f : v; }
__device__ __forceinline__ float ld_relaxed(const float* p) { float v; asm volatile("ld.relaxed.gpu.global.f32 %0, [%1];" : "=f"(v) : "l"(p) : "memory"); return v; }
__device__ __forceinline__ float2 ld_relaxed2(const float2* p) {
  unsigned long long v; asm volatile("ld.relaxed.gpu.global.u64 %0, [%1];" : "=l"(v) : "l"(p) : "memory");
  return make_float2(__uint_as_float((uint32_t)v), __uint_as_float((uint32_t)(v >> 32)));
}
__device__ __forceinline__ unsigned ld_acquire(const unsigned* p) { unsigned v; asm volatile("ld.acquire.gpu.global.u32 %0, [%1];" : "=r"(v) : "l"(p) : "memory"); return v; }
__device__ __forceinline__ void red_relaxed(unsigned* p) { asm volatile("red.relaxed.gpu.global.add.u32 [%0], 1;" ::"l"(p) : "memory"); }
__device__ __forceinline__ void red_release(unsigned* p) { asm volatile("red.release.gpu.global.add.u32 [%0], 1;" ::"l"(p) : "memory"); }
__device__ __forceinline__ float2 stat_ld(const float2* st, int row, int q) {
  float2 a = __ldcg(st + (2 * q) * S_ + row), b = __ldcg(st + (2 * q + 1) * S_ + row);
  return make_float2(a.x + b.x, a.y + b.y);
}
__device__ __forceinline__ void stat_fin(float2 a, float& mu, float& var) {
  float s = a.x, ss = a.y;
  s += __shfl_xor_sync(~0u, s, 1); ss += __shfl_xor_sync(~0u, ss, 1);
  s += __shfl_xor_sync(~0u, s, 2); ss += __shfl_xor_sync(~0u, ss, 2);
  mu = s * (1.f / D_);
  var = fmaxf(ss * (1.f / D_) - mu * mu, 0.f);
}
__device__ __forceinline__ void row_stats(const float2* st, int row, int q, float& mu, float& var) { stat_fin(stat_ld(st, row, q), mu, var); }

#define TL(k, s)
#define TR(c, i)
#define TR1(c, i)
__device__ __forceinline__ void wgmma_rs_n24_tb(float (&d)[12], uint32_t a0, uint32_t a1, uint32_t a2, uint32_t a3, uint64_t db, int sd) {
  asm volatile("{\n.reg .pred p;\nsetp.ne.b32 p, %17, 0;\n"
    "wgmma.mma_async.sync.aligned.m64n24k16.f32.bf16.bf16 {%0, %1, %2, %3, %4, %5, %6, %7, %8, %9, %10, %11}, {%12, %13, %14, %15}, %16, p, 1, 1, 1;\n}\n"
    : "+f"(d[0]), "+f"(d[1]), "+f"(d[2]), "+f"(d[3]), "+f"(d[4]), "+f"(d[5]), "+f"(d[6]), "+f"(d[7]), "+f"(d[8]), "+f"(d[9]), "+f"(d[10]), "+f"(d[11])
    : "r"(a0), "r"(a1), "r"(a2), "r"(a3), "l"(db), "r"(sd));
}

__device__ __forceinline__ void wgmma_rs_n64_tb(float (&d)[32], uint32_t a0, uint32_t a1, uint32_t a2, uint32_t a3, uint64_t db, int sd) {
  asm volatile("{\n.reg .pred p;\nsetp.ne.b32 p, %37, 0;\n"
    "wgmma.mma_async.sync.aligned.m64n64k16.f32.bf16.bf16 {%0, %1, %2, %3, %4, %5, %6, %7, %8, %9, %10, %11, %12, %13, %14, %15, %16, %17, %18, %19, %20, %21, %22, %23, %24, %25, %26, %27, %28, %29, %30, %31}, {%32, %33, %34, %35}, %36, p, 1, 1, 1;\n}\n"
    : "+f"(d[0]), "+f"(d[1]), "+f"(d[2]), "+f"(d[3]), "+f"(d[4]), "+f"(d[5]), "+f"(d[6]), "+f"(d[7]), "+f"(d[8]), "+f"(d[9]), "+f"(d[10]), "+f"(d[11]), "+f"(d[12]), "+f"(d[13]), "+f"(d[14]), "+f"(d[15]), "+f"(d[16]), "+f"(d[17]), "+f"(d[18]), "+f"(d[19]), "+f"(d[20]), "+f"(d[21]), "+f"(d[22]), "+f"(d[23]), "+f"(d[24]), "+f"(d[25]), "+f"(d[26]), "+f"(d[27]), "+f"(d[28]), "+f"(d[29]), "+f"(d[30]), "+f"(d[31])
    : "r"(a0), "r"(a1), "r"(a2), "r"(a3), "l"(db), "r"(sd));
}

__device__ __forceinline__ void wgmma_ss_n128(float (&d)[64], uint64_t da, uint64_t db, int sd) {
  asm volatile("{\n.reg .pred p;\nsetp.ne.b32 p, %66, 0;\n"
    "wgmma.mma_async.sync.aligned.m64n128k16.f32.bf16.bf16 {%0, %1, %2, %3, %4, %5, %6, %7, %8, %9, %10, %11, %12, %13, %14, %15, %16, %17, %18, %19, %20, %21, %22, %23, %24, %25, %26, %27, %28, %29, %30, %31, %32, %33, %34, %35, %36, %37, %38, %39, %40, %41, %42, %43, %44, %45, %46, %47, %48, %49, %50, %51, %52, %53, %54, %55, %56, %57, %58, %59, %60, %61, %62, %63}, %64, %65, p, 1, 1, 0, 0;\n}\n"
    : "+f"(d[0]), "+f"(d[1]), "+f"(d[2]), "+f"(d[3]), "+f"(d[4]), "+f"(d[5]), "+f"(d[6]), "+f"(d[7]), "+f"(d[8]), "+f"(d[9]), "+f"(d[10]), "+f"(d[11]), "+f"(d[12]), "+f"(d[13]), "+f"(d[14]), "+f"(d[15]), "+f"(d[16]), "+f"(d[17]), "+f"(d[18]), "+f"(d[19]), "+f"(d[20]), "+f"(d[21]), "+f"(d[22]), "+f"(d[23]), "+f"(d[24]), "+f"(d[25]), "+f"(d[26]), "+f"(d[27]), "+f"(d[28]), "+f"(d[29]), "+f"(d[30]), "+f"(d[31]), "+f"(d[32]), "+f"(d[33]), "+f"(d[34]), "+f"(d[35]), "+f"(d[36]), "+f"(d[37]), "+f"(d[38]), "+f"(d[39]), "+f"(d[40]), "+f"(d[41]), "+f"(d[42]), "+f"(d[43]), "+f"(d[44]), "+f"(d[45]), "+f"(d[46]), "+f"(d[47]), "+f"(d[48]), "+f"(d[49]), "+f"(d[50]), "+f"(d[51]), "+f"(d[52]), "+f"(d[53]), "+f"(d[54]), "+f"(d[55]), "+f"(d[56]), "+f"(d[57]), "+f"(d[58]), "+f"(d[59]), "+f"(d[60]), "+f"(d[61]), "+f"(d[62]), "+f"(d[63])
    : "l"(da), "l"(db), "r"(sd));
}

__device__ __forceinline__ void wgmma_rs_n64(float (&d)[32], uint32_t a0, uint32_t a1, uint32_t a2, uint32_t a3, uint64_t db, int sd) {
  asm volatile("{\n.reg .pred p;\nsetp.ne.b32 p, %37, 0;\n"
    "wgmma.mma_async.sync.aligned.m64n64k16.f32.bf16.bf16 {%0, %1, %2, %3, %4, %5, %6, %7, %8, %9, %10, %11, %12, %13, %14, %15, %16, %17, %18, %19, %20, %21, %22, %23, %24, %25, %26, %27, %28, %29, %30, %31}, {%32, %33, %34, %35}, %36, p, 1, 1, 0;\n}\n"
    : "+f"(d[0]), "+f"(d[1]), "+f"(d[2]), "+f"(d[3]), "+f"(d[4]), "+f"(d[5]), "+f"(d[6]), "+f"(d[7]), "+f"(d[8]), "+f"(d[9]), "+f"(d[10]), "+f"(d[11]), "+f"(d[12]), "+f"(d[13]), "+f"(d[14]), "+f"(d[15]), "+f"(d[16]), "+f"(d[17]), "+f"(d[18]), "+f"(d[19]), "+f"(d[20]), "+f"(d[21]), "+f"(d[22]), "+f"(d[23]), "+f"(d[24]), "+f"(d[25]), "+f"(d[26]), "+f"(d[27]), "+f"(d[28]), "+f"(d[29]), "+f"(d[30]), "+f"(d[31])
    : "r"(a0), "r"(a1), "r"(a2), "r"(a3), "l"(db), "r"(sd));
}

__device__ __forceinline__ void wgmma_ss_n72_tb(float (&d)[36], uint64_t da, uint64_t db, int sd) {
  asm volatile("{\n.reg .pred p;\nsetp.ne.b32 p, %38, 0;\n"
    "wgmma.mma_async.sync.aligned.m64n72k16.f32.bf16.bf16 {%0, %1, %2, %3, %4, %5, %6, %7, %8, %9, %10, %11, %12, %13, %14, %15, %16, %17, %18, %19, %20, %21, %22, %23, %24, %25, %26, %27, %28, %29, %30, %31, %32, %33, %34, %35}, %36, %37, p, 1, 1, 0, 1;\n}\n"
    : "+f"(d[0]), "+f"(d[1]), "+f"(d[2]), "+f"(d[3]), "+f"(d[4]), "+f"(d[5]), "+f"(d[6]), "+f"(d[7]), "+f"(d[8]), "+f"(d[9]), "+f"(d[10]), "+f"(d[11]), "+f"(d[12]), "+f"(d[13]), "+f"(d[14]), "+f"(d[15]), "+f"(d[16]), "+f"(d[17]), "+f"(d[18]), "+f"(d[19]), "+f"(d[20]), "+f"(d[21]), "+f"(d[22]), "+f"(d[23]), "+f"(d[24]), "+f"(d[25]), "+f"(d[26]), "+f"(d[27]), "+f"(d[28]), "+f"(d[29]), "+f"(d[30]), "+f"(d[31]), "+f"(d[32]), "+f"(d[33]), "+f"(d[34]), "+f"(d[35])
    : "l"(da), "l"(db), "r"(sd));
}

__device__ __forceinline__ void wgmma_ss_n224_tb(float (&d)[112], uint64_t da, uint64_t db, int sd) {
  asm volatile("{\n.reg .pred p;\nsetp.ne.b32 p, %114, 0;\n"
    "wgmma.mma_async.sync.aligned.m64n224k16.f32.bf16.bf16 {%0, %1, %2, %3, %4, %5, %6, %7, %8, %9, %10, %11, %12, %13, %14, %15, %16, %17, %18, %19, %20, %21, %22, %23, %24, %25, %26, %27, %28, %29, %30, %31, %32, %33, %34, %35, %36, %37, %38, %39, %40, %41, %42, %43, %44, %45, %46, %47, %48, %49, %50, %51, %52, %53, %54, %55, %56, %57, %58, %59, %60, %61, %62, %63, %64, %65, %66, %67, %68, %69, %70, %71, %72, %73, %74, %75, %76, %77, %78, %79, %80, %81, %82, %83, %84, %85, %86, %87, %88, %89, %90, %91, %92, %93, %94, %95, %96, %97, %98, %99, %100, %101, %102, %103, %104, %105, %106, %107, %108, %109, %110, %111}, %112, %113, p, 1, 1, 0, 1;\n}\n"
    : "+f"(d[0]), "+f"(d[1]), "+f"(d[2]), "+f"(d[3]), "+f"(d[4]), "+f"(d[5]), "+f"(d[6]), "+f"(d[7]), "+f"(d[8]), "+f"(d[9]), "+f"(d[10]), "+f"(d[11]), "+f"(d[12]), "+f"(d[13]), "+f"(d[14]), "+f"(d[15]), "+f"(d[16]), "+f"(d[17]), "+f"(d[18]), "+f"(d[19]), "+f"(d[20]), "+f"(d[21]), "+f"(d[22]), "+f"(d[23]), "+f"(d[24]), "+f"(d[25]), "+f"(d[26]), "+f"(d[27]), "+f"(d[28]), "+f"(d[29]), "+f"(d[30]), "+f"(d[31]), "+f"(d[32]), "+f"(d[33]), "+f"(d[34]), "+f"(d[35]), "+f"(d[36]), "+f"(d[37]), "+f"(d[38]), "+f"(d[39]), "+f"(d[40]), "+f"(d[41]), "+f"(d[42]), "+f"(d[43]), "+f"(d[44]), "+f"(d[45]), "+f"(d[46]), "+f"(d[47]), "+f"(d[48]), "+f"(d[49]), "+f"(d[50]), "+f"(d[51]), "+f"(d[52]), "+f"(d[53]), "+f"(d[54]), "+f"(d[55]), "+f"(d[56]), "+f"(d[57]), "+f"(d[58]), "+f"(d[59]), "+f"(d[60]), "+f"(d[61]), "+f"(d[62]), "+f"(d[63]), "+f"(d[64]), "+f"(d[65]), "+f"(d[66]), "+f"(d[67]), "+f"(d[68]), "+f"(d[69]), "+f"(d[70]), "+f"(d[71]), "+f"(d[72]), "+f"(d[73]), "+f"(d[74]), "+f"(d[75]), "+f"(d[76]), "+f"(d[77]), "+f"(d[78]), "+f"(d[79]), "+f"(d[80]), "+f"(d[81]), "+f"(d[82]), "+f"(d[83]), "+f"(d[84]), "+f"(d[85]), "+f"(d[86]), "+f"(d[87]), "+f"(d[88]), "+f"(d[89]), "+f"(d[90]), "+f"(d[91]), "+f"(d[92]), "+f"(d[93]), "+f"(d[94]), "+f"(d[95]), "+f"(d[96]), "+f"(d[97]), "+f"(d[98]), "+f"(d[99]), "+f"(d[100]), "+f"(d[101]), "+f"(d[102]), "+f"(d[103]), "+f"(d[104]), "+f"(d[105]), "+f"(d[106]), "+f"(d[107]), "+f"(d[108]), "+f"(d[109]), "+f"(d[110]), "+f"(d[111])
    : "l"(da), "l"(db), "r"(sd));
}

constexpr int K1_ST = 4, K1_STAGE = 16384 + 4 * 8192;
constexpr int K1_SMEM = K1_ST * K1_STAGE + 224 * 4 + 1024 + 128;
__global__ void __launch_bounds__(384, 1)
k1_qkv(const __grid_constant__ CUtensorMap mx, const __grid_constant__ CUtensorMap mw0, const __grid_constant__ CUtensorMap mw1, const bf16* __restrict__ x, const bf16* __restrict__ wqkv,
       const bf16* __restrict__ wo, const bf16* __restrict__ w1, const bf16* __restrict__ w2) {
  uint8_t* const sm = dsm;
  float* colc = (float*)(sm + K1_ST * K1_STAGE);
  float2* rowc = (float2*)(colc + 224);
  const uint32_t bars = s2u(sm + K1_ST * K1_STAGE + 224 * 4 + 1024);
  const int ti = blockIdx.x >> 3, tj = blockIdx.x & 7;
  TL(0, 0);
  const int warp = threadIdx.x >> 5, lane = threadIdx.x & 31;
  if (threadIdx.x == 0) {
    for (int s = 0; s < K1_ST; s++) { mb_init(bars + s * 8, 1); mb_init(bars + 64 + s * 8, 2); }
    mb_init(bars + 120, 1);
    fence_mb_init();
  }
  __syncthreads();
  pdl_launch();
  if (warp >= 8) {
    if (warp == 8) {
      if (lane == 0) {
        for (int ks = 0; ks < 9; ks++) {
          int s = ks % K1_ST;
          mb_wait(bars + 64 + s * 8, ((ks / K1_ST) & 1) ^ 1);
          mb_expect(bars + s * 8, K1_STAGE);
          uint32_t dst = s2u(sm) + s * K1_STAGE;
          tma2d(dst, &mx, ks * 64, ti * 128, bars + s * 8);
          for (int a = 0; a < 4; a++) tma3d(dst + 16384 + a * 8192, (tj & 1) ? &mw1 : &mw0, (tj & 1) * 208 + a * 64, tj >> 1, ks * 64, bars + s * 8);
        }
      }
    } else if (warp == 9) {
      if (lane < 27) {
        float acc[8] = {0, 0, 0, 0, 0, 0, 0, 0};
        const uint4* p = (const uint4*)(wqkv + (size_t)(ti * 36) * 1728 + tj * 216 + lane * 8);
        uint4 w[36];
#pragma unroll
        for (int r = 0; r < 36; r++) w[r] = __ldg(p + r * 216);
#pragma unroll
        for (int r = 0; r < 36; r++) {
          const uint4 v = w[r];
          acc[0] += blo(v.x); acc[1] += bhi(v.x); acc[2] += blo(v.y); acc[3] += bhi(v.y);
          acc[4] += blo(v.z); acc[5] += bhi(v.z); acc[6] += blo(v.w); acc[7] += bhi(v.w);
        }
        float4* o = (float4*)(g_csq + ti * 1728 + tj * 216 + lane * 8);
        __stcg(o, make_float4(nz(acc[0]), nz(acc[1]), nz(acc[2]), nz(acc[3])));
        __stcg(o + 1, make_float4(nz(acc[4]), nz(acc[5]), nz(acc[6]), nz(acc[7])));
      }
      TR1(lane == 0, 20);
    } else {
      int row = ti * 128 + tj * 16 + (warp - 10) * 8 + (lane >> 2);
      const uint4* p = (const uint4*)(x + (size_t)row * D_) + (lane & 3);
      uint4 v[18];
#pragma unroll
      for (int c = 0; c < 18; c++) v[c] = __ldg(p + c * 4);
      float s = 0.f;
#pragma unroll
      for (int c = 0; c < 18; c++)
        s += blo(v[c].x) + bhi(v[c].x) + blo(v[c].y) + bhi(v[c].y) + blo(v[c].z) + bhi(v[c].z) + blo(v[c].w) + bhi(v[c].w);
      s += __shfl_xor_sync(~0u, s, 1); s += __shfl_xor_sync(~0u, s, 2);
      float mu = s * (1.f / D_), ss = 0.f;
#pragma unroll
      for (int c = 0; c < 18; c++) {
        uint32_t w4[4] = {v[c].x, v[c].y, v[c].z, v[c].w};
#pragma unroll
        for (int e = 0; e < 4; e++) { float a = blo(w4[e]) - mu, b = bhi(w4[e]) - mu; ss = fmaf(a, a, ss); ss = fmaf(b, b, ss); }
      }
      ss += __shfl_xor_sync(~0u, ss, 1); ss += __shfl_xor_sync(~0u, ss, 2);
      if ((lane & 3) == 0) __stcg(g_st_x + row, make_float2(mu, nz(rsqrtf(ss * (1.f / D_) + LN_EPS))));
      TR1(lane == 0, 21);
    }
    if (warp > 8) {
      const int od = (tj & 1) * 8;
      const int t = threadIdx.x - 288;
      float cs[3];
      float2 st[2];
      int n = 0;
      bool ok;
      mb_wait(bars + 120, 0);
      do {
        if (n) __nanosleep(300);
        float v[3][16];
#pragma unroll
        for (int u = 0; u < 3; u++)
#pragma unroll
          for (int p = 0; p < 16; p++) v[u][p] = ld_relaxed(g_csq + tj * 216 + min(t + u * 96, 215) + p * 1728);
        st[0] = ld_relaxed2(g_st_x + ti * 128 + t); st[1] = ld_relaxed2(g_st_x + ti * 128 + 96 + (t & 31));
        ok = __float_as_uint(st[0].y) != 0u && __float_as_uint(st[1].y) != 0u;
#pragma unroll
        for (int u = 0; u < 3; u++) {
          cs[u] = 0.f;
#pragma unroll
          for (int p = 0; p < 16; p++) { cs[u] += v[u][p]; ok = ok && __float_as_uint(v[u][p]) != 0u; }
        }
      } while (!ok && ++n < (SPIN_MAX >> 4));
      colc[t + od] = cs[0]; colc[t + 96 + od] = cs[1];
      if (t < 24) colc[t + 192 + od] = cs[2]; else if (t < 32) colc[t + 192 - od * 27] = 0.f;
      rowc[t] = st[0];
      if (t < 32) rowc[96 + t] = st[1];
      __syncwarp();
      asm volatile("bar.arrive 1, 352;" ::: "memory");
      TR1(lane == 0, 22);
    }
  } else {
    const int wg = __reduce_or_sync(~0u, warp >> 2);
    uint4 rt[4];
    float acc[112];
    TR1(threadIdx.x == 0, 1);
    const uint64_t da = mkdesc(s2u(sm) + wg * 8192, 16, 1024, 1), db = mkdesc(s2u(sm) + 16384, 8192, 1024, 1);
#pragma unroll
    for (int ks = 0; ks < 9; ks++) {
      const int s = ks % K1_ST;
      mb_wait(bars + s * 8, (ks / K1_ST) & 1);
      TR1(threadIdx.x == 0, 2 + ks);
      wg_fence();
#pragma unroll
      for (int k = 0; k < 4; k++) wgmma_ss_n224_tb(acc, da + s * (K1_STAGE / 16) + k * 2, db + s * (K1_STAGE / 16) + k * 128, (ks | k) != 0);
      wg_commit();
      if (ks == 5 && threadIdx.x == 0) mb_arrive(bars + 120);
      if (ks == 4) {
#pragma unroll
    for (int i = 0; i < 4; i++) {
      int c = blockIdx.x * 972 + min(i * 256 + (int)threadIdx.x, 971);
      int m = c / 41472, r = c % 41472, ct = r / 5184, r2 = r % 5184, kg = r2 / 72, r3 = r2 % 72;
      const bf16* w = (m == 0 ? wo : (m == 1 ? w1 : w2)) + (size_t)(kg * 8 + (r3 & 7)) * D_ + ct * 72 + (r3 >> 3) * 8;
      asm volatile("ld.global.nc.v4.u32 {%0,%1,%2,%3}, [%4];" : "=r"(rt[i].x), "=r"(rt[i].y), "=r"(rt[i].z), "=r"(rt[i].w) : "l"(w));
    }
      }
      if (ks > 0) { wg_wait<1>(); if ((threadIdx.x & 127) == 0) mb_arrive(bars + 64 + ((ks - 1) % K1_ST) * 8); }
    }
    TL(0, 1);
    TR1(threadIdx.x == 0, 11);
#pragma unroll
    for (int i = 0; i < 4; i++)
      if (i * 256 + threadIdx.x < 972) ((uint4*)g_wimg)[blockIdx.x * 972 + i * 256 + threadIdx.x] = rt[i];
    if (blockIdx.x == 1 && threadIdx.x < 144) { ((uint4*)(g_gs + 2 * D_))[threadIdx.x] = make_uint4(0, 0, 0, 0); ((uint4*)(g_gs + S_ * D_))[threadIdx.x] = make_uint4(0, 0, 0, 0); }
    if (blockIdx.x == 0 && threadIdx.x < 64) g_cm[threadIdx.x] = 0;
    const int g = lane >> 2, q = lane & 3, od = (tj & 1) * 8;
    TR1(threadIdx.x == 0, 12);
    wg_wait<0>();
    reg_fence(acc);
    bar_sync(1, 352);
    const float2 st0 = rowc[warp * 16 + g], st1 = rowc[warp * 16 + g + 8];
    TL(0, 2);
    TR1(threadIdx.x == 0, 13);
    uint32_t* stg = (uint32_t*)sm + warp * 16 * 132;
    constexpr float QS = 0.23570226039551584f * 1.4426950408889634f;
    const float rq0 = st0.y * QS, rq1 = st1.y * QS;
#pragma unroll
    for (int ch = 0; ch < 3; ch++) {
#pragma unroll
    for (int c = ch ? ch * 9 + 1 : 0; c < ch * 9 + 10; c++) {
      const float2 cc = *(const float2*)(colc + c * 8 + q * 2);
      const bool isq = tj * 216 - od + c * 8 < 576;
      const float ra = isq ? rq0 : st0.y, rb = isq ? rq1 : st1.y;
      stg[g * 132 + c * 4 + q] = pack2(fmaf(-st0.x, cc.x, acc[c * 4 + 0]) * ra, fmaf(-st0.x, cc.y, acc[c * 4 + 1]) * ra);
      stg[(g + 8) * 132 + c * 4 + q] = pack2(fmaf(-st1.x, cc.x, acc[c * 4 + 2]) * rb, fmaf(-st1.x, cc.y, acc[c * 4 + 3]) * rb);
    }
    __syncwarp();
#pragma unroll
    for (int it = ch * 2; it < ch * 2 + 2; it++) {
      int lr = (it & 1) * 8 + (lane & 7), hd = (it >> 1) * 4 + (lane >> 3);
      const uint32_t* src = stg + lr * 132 + hd * 9 + (od >> 1);
      uint32_t w[9];
#pragma unroll
      for (int e = 0; e < 9; e++) w[e] = src[e];
      int gh = tj * 12 + hd, type = gh >> 5, head = gh & 31;
      int rg = ti * 16 + warp * 2 + (it & 1);
      uint4* dst = (uint4*)g_qkv + ((size_t)(gh * 256 + rg) * 3) * 8 + (lane & 7);
      dst[0] = make_uint4(w[0], w[1], w[2], w[3]);
      dst[8] = make_uint4(w[4], w[5], w[6], w[7]);
      const bool pk = type == 1 && ((POLY_MASK >> ((rg & 7) * 2 + (lane & 1))) & 1);
      dst[16] = make_uint4(w[8], pk ? 0x3f803f80u : (type ? 0x00003f80u : 0u), type == 1 ? 0x3f803f80u : 0u, 0u);
      if (tj < 2 || tj > 5) continue;
      float n2 = 0.f;
#pragma unroll
      for (int e = 0; e < 9; e++) { n2 = fmaf(blo(w[e]), blo(w[e]), n2); n2 = fmaf(bhi(w[e]), bhi(w[e]), n2); }
      unsigned u = __float_as_uint(n2);
      u = max(u, __shfl_xor_sync(~0u, u, 1)); u = max(u, __shfl_xor_sync(~0u, u, 2)); u = max(u, __shfl_xor_sync(~0u, u, 4));
      if (type == 1 && (lane & 7) == 0) g_kmax2[head * 256 + rg] = __uint_as_float(u);
    }
    }
    TL(0, 3);
    TR1(threadIdx.x == 0, 15);
  }
}

constexpr int K2_SMEM = 2 * 98304 + 32768 + 256;
__device__ __forceinline__ float ex2_poly(float t) {
  uint32_t fl, r;
  asm("and.b32 %0, %1, 0xffffe000;" : "=r"(fl) : "r"(__float_as_uint(t)));
  float f = t - __uint_as_float(fl);
  float p = fmaf(f, 0.07802411f, 0.22606714f);
  p = fmaf(p, f, 0.69583386f);
  p = fmaf(p, f, 0.99992514f);
  asm("mad.lo.u32 %0, %1, 1024, %2;" : "=r"(r) : "r"(fl), "r"(__float_as_uint(p)));
  return __uint_as_float(r);
}
template <bool FAST>
__device__ __forceinline__ void exp_tile(float (&s)[32]) {
#pragma unroll
  for (int i = 0; i < 32; i++) {
    s[i] = (FAST && ((POLY_MASK >> ((i >> 2) * 2 + (i & 1))) & 1)) ? ex2_poly(s[i]) : ex2(s[i]);
    asm volatile("" : "+f"(s[i]));
  }
}
template <bool FAST>
__device__ __forceinline__ void attn_step(float (&cur)[32], float (&nxt)[32], float (&o)[12], const uint32_t (&qa)[6], uint64_t dk, uint64_t dv, uint32_t za, uint32_t zb) {
  uint32_t p[16];
#pragma unroll
  for (int i = 0; i < 16; i++) p[i] = pack2(cur[2 * i], cur[2 * i + 1]);
  wg_fence();
#pragma unroll
  for (int k = 0; k < 4; k++) wgmma_rs_n24_tb(o, p[4 * k], p[4 * k + 1], p[4 * k + 2], p[4 * k + 3], dv + k * 48, 1);
  wgmma_rs_n64(cur, qa[0], qa[1], qa[2], qa[3], dk, 0);
  wgmma_rs_n64(cur, qa[4], qa[5], 0u, 0u, dk + 16 - (8ull << 16), 1);
  wg_commit();
  sched_fence(za);
  exp_tile<FAST>(nxt);
  sched_fence(zb);
  wg_wait<0>();
  reg_fence(cur);
  reg_fence(o);
}
__device__ __forceinline__ void put_o(const float (&o)[12], uint32_t* op) {
  const int lane = threadIdx.x & 31;
  float l0 = __shfl_sync(~0u, o[8], (lane & ~3) | 1), l1 = __shfl_sync(~0u, o[10], (lane & ~3) | 1);
  float i0 = 1.f / l0, i1 = 1.f / l1;
  op[0] = pack2(o[0] * i0, o[1] * i0); op[4] = pack2(o[4] * i0, o[5] * i0);
  op[8 * 288] = pack2(o[2] * i1, o[3] * i1); op[8 * 288 + 4] = pack2(o[6] * i1, o[7] * i1);
  if ((lane & 3) == 0) { op[8] = pack2(o[8] * i0, o[9] * i0); op[8 * 288 + 8] = pack2(o[10] * i1, o[11] * i1); }
}
__device__ __forceinline__ void get_q(uint32_t a, uint32_t (&qa)[6]) {
  asm volatile("ld.shared.b32 %0, [%6];\nld.shared.b32 %2, [%6+128];\nld.shared.b32 %4, [%6+256];\nld.shared.b32 %1, [%6+512];\nld.shared.b32 %3, [%6+640];\nld.shared.b32 %5, [%6+768];"
               : "=r"(qa[0]), "=r"(qa[1]), "=r"(qa[2]), "=r"(qa[3]), "=r"(qa[4]), "=r"(qa[5]) : "r"(a) : "memory");
}
template <bool FAST, int NT>
__device__ __forceinline__ void attn_pass(uint32_t (&qa)[6], uint32_t qw2, uint32_t* op, const uint4& z) {
  const uint32_t ks = s2u(dsm), bars = ks + 2 * 98304 + 32768;
  float s0[32], s1[32], o[12];
  const uint64_t dk = mkdesc(ks, 128, 384, 0), dv = mkdesc(ks + 98304, 384, 128, 0);
  mb_wait(bars, 0);
  wg_fence();
  wgmma_rs_n64(s0, qa[0], qa[1], qa[2], qa[3], dk, 0);
  wgmma_rs_n64(s0, qa[4], qa[5], 0u, 0u, dk + 16 - (8ull << 16), 1);
  wgmma_rs_n64(s1, qa[0], qa[1], qa[2], qa[3], dk + 192, 0);
  wgmma_rs_n64(s1, qa[4], qa[5], 0u, 0u, dk + 192 + 16 - (8ull << 16), 1);
  wg_commit();
  wg_wait<0>();
  reg_fence(s0);
  reg_fence(s1);
  exp_tile<FAST>(s0);
#pragma unroll 1
  for (int t = 0; t < NT; t++) {
#pragma unroll
    for (int i = 0; i < 12; i++) o[i] = 0.f;
    uint64_t v = dv;
#pragma unroll 1
    for (uint32_t b = bars + 8; b != bars + 128; b += 8) {
      mb_wait(b, 0);
      attn_step<FAST>(s0, s1, o, qa, v + (dk - dv) + 384, v, z.x, z.y);
      attn_step<FAST>(s1, s0, o, qa, v + (dk - dv) + 576, v + 192, z.z, z.w);
      v += 384;
    }
    if (NT > 1) get_q(qw2, qa);
    attn_step<FAST>(s0, s1, o, qa, dk, dv + 15 * 384, z.x, z.y);
    attn_step<FAST>(s1, s0, o, qa, dk + 192, dv + 15 * 384 + 192, z.z, z.w);
    put_o(o, op + t * 64 * 288);
  }
}
__device__ __forceinline__ void attn_rowmax(uint32_t qs, uint32_t ks, uint32_t bars, float& m0, float& m1) {
  float s[64];
  m0 = -INFINITY; m1 = -INFINITY;
  const uint64_t dq = mkdesc(qs, 128, 512, 0);
#pragma unroll 1
  for (int j = 0; j < 16; j++) {
    mb_wait(bars + j * 8, 0);
    wg_fence();
    uint64_t dk = mkdesc(ks + j * 6144, 128, 384, 0);
    wgmma_ss_n128(s, dq, dk, 0);
    wgmma_ss_n128(s, dq + 16, dk + 16 - (8ull << 16), 1);
    wg_commit();
    wg_wait<0>();
    reg_fence(s);
#pragma unroll
    for (int i = 0; i < 16; i++) { m0 = fmaxf(m0, fmaxf(s[4 * i], s[4 * i + 1])); m1 = fmaxf(m1, fmaxf(s[4 * i + 2], s[4 * i + 3])); }
  }
  m0 = fmaxf(m0, __shfl_xor_sync(~0u, m0, 1)); m0 = fmaxf(m0, __shfl_xor_sync(~0u, m0, 2));
  m1 = fmaxf(m1, __shfl_xor_sync(~0u, m1, 1)); m1 = fmaxf(m1, __shfl_xor_sync(~0u, m1, 2));
}
__device__ __forceinline__ void put_q(uint32_t a, const uint32_t (&qa)[6]) {
  asm volatile("st.shared.b32 [%0], %1;\nst.shared.b32 [%0+128], %3;\nst.shared.b32 [%0+256], %5;\nst.shared.b32 [%0+384], %7;\n"
               "st.shared.b32 [%0+512], %2;\nst.shared.b32 [%0+640], %4;\nst.shared.b32 [%0+768], %6;\nst.shared.b32 [%0+896], %7;\n"
               ::"r"(a), "r"(qa[0]), "r"(qa[1]), "r"(qa[2]), "r"(qa[3]), "r"(qa[4]), "r"(qa[5]), "r"(0u) : "memory");
}
__device__ __forceinline__ float bf_round(float x) { return __bfloat162float(__float2bfloat16_rn(x)); }

__global__ void __launch_bounds__(512, 1)
k2_attn(const bf16* __restrict__ w1, const bf16* __restrict__ w3, const bf16* __restrict__ w4, const uint4 z) {
  uint8_t* const sm = dsm;
  const int warp = threadIdx.x >> 5, lane = threadIdx.x & 31;
  TL(1, 0);
  if (blockIdx.x >= 128) {
    pdl_launch();
    const int hb = blockIdx.x - 128;
    float* red = (float*)sm;
    const int t = threadIdx.x;
    if (t < 432 + 54) {
      const bool is3 = t < 432;
      const int chunk = is3 ? t % 144 : (t - 432) % 18, kg = is3 ? t / 144 : (t - 432) / 18;
      const int ld = is3 ? F_ / 8 : D_ / 8;
      const uint4* p = (const uint4*)(is3 ? w3 + hb * 1152 : w1 + hb * 144) + chunk + (size_t)kg * 192 * ld;
      float acc[8] = {0, 0, 0, 0, 0, 0, 0, 0};
#pragma unroll 16
      for (int r = 0; r < 192; r++) {
        uint4 v = __ldg(p + (size_t)r * ld);
        acc[0] += blo(v.x); acc[1] += bhi(v.x); acc[2] += blo(v.y); acc[3] += bhi(v.y);
        acc[4] += blo(v.z); acc[5] += bhi(v.z); acc[6] += blo(v.w); acc[7] += bhi(v.w);
      }
      float* o = red + kg * 1296 + (is3 ? 0 : 1152) + chunk * 8;
#pragma unroll
      for (int e = 0; e < 8; e++) o[e] = acc[e];
    }
    __syncthreads();
    pdl_wait();
    for (int c = t; c < 1296; c += 512) {
      float v = red[c] + red[1296 + c] + red[2592 + c];
      if (c < 1152) g_cs3[hb * 1152 + c] = v; else g_cs1[hb * 144 + c - 1152] = v;
    }
    TL(1, 4);
    return;
  }
  const int head = blockIdx.x >> 2, qb = blockIdx.x & 3;
  const uint32_t ks = s2u(sm), vs = ks + 98304, bars = ks + 2 * 98304 + 32768;
  if (threadIdx.x == 0) {
    for (int c = 0; c < 16; c++) mb_init(bars + c * 8, 1);
    fence_mb_init();
    const int b = blockIdx.x;
    prefetch_l2((const uint8_t*)w4 + b * 41472, 41472);
  }
  __syncthreads();
  pdl_wait();
  pdl_launch();
  TL(1, 1);
  if (threadIdx.x == 0) {
    const uint8_t* kg = (const uint8_t*)g_qkv + (size_t)(32 + head) * 98304;
    const uint8_t* vg = (const uint8_t*)g_qkv + (size_t)(64 + head) * 98304;
    for (int c = 0; c < 16; c++) {
      mb_expect(bars + c * 8, 12288);
      bulk_g2s(ks + c * 6144, kg + c * 6144, 6144, bars + c * 8);
      bulk_g2s(vs + c * 6144, vg + c * 6144, 6144, bars + c * 8);
    }
  }
  if (threadIdx.x >= 64 && threadIdx.x < 64 + 54) ((uint4*)g_csq)[blockIdx.x * 54 + threadIdx.x - 64] = make_uint4(0, 0, 0, 0);
  if (threadIdx.x >= 128 && threadIdx.x < 136) ((uint4*)g_st_x)[blockIdx.x * 8 + threadIdx.x - 128] = make_uint4(0, 0, 0, 0);
  const int wg = __reduce_or_sync(~0u, warp >> 2), g = lane >> 2, q = lane & 3;
  const uint32_t qs = ks + 2 * 98304 + wg * 4096, qw = qs + (warp & 3) * 1024 + lane * 4;
  const int row0 = qb * 512 + wg * 128 + (warp & 3) * 16;
  uint32_t* op = (uint32_t*)(g_o + (size_t)(row0 + g) * D_ + head * 18) + q;
  uint32_t qa[2][6];
#pragma unroll
  for (int t = 0; t < 2; t++) {
    const uint32_t* qp = (const uint32_t*)g_qkv + (size_t)(head * 256 + (row0 >> 3) + t * 8) * 96 + lane;
    qa[t][0] = __ldcg(qp); qa[t][1] = __ldcg(qp + 96); qa[t][2] = __ldcg(qp + 32); qa[t][3] = __ldcg(qp + 128); qa[t][4] = __ldcg(qp + 64); qa[t][5] = __ldcg(qp + 160);
  }
  unsigned km = 0;
#pragma unroll
  for (int e = 0; e < 8; e++) km = max(km, __float_as_uint(__ldcg(g_kmax2 + head * 256 + e * 32 + lane)));
  km = __reduce_max_sync(~0u, km);
  const float kmax2 = __uint_as_float(km);
  int unsafe = 0;
  uint32_t sh[4];
#pragma unroll
  for (int t = 0; t < 4; t++) {
    const uint32_t a = qa[t >> 1][t & 1], b = qa[t >> 1][2 + (t & 1)], c = qa[t >> 1][4 + (t & 1)];
    float n = blo(a) * blo(a) + bhi(a) * bhi(a) + blo(b) * blo(b) + bhi(b) * bhi(b) + blo(c) * blo(c) + bhi(c) * bhi(c);
    n += __shfl_xor_sync(~0u, n, 1); n += __shfl_xor_sync(~0u, n, 2);
    float bd = sqrtf(n * kmax2) * 1.01f;
    unsafe |= !(bd <= 60.f);
    sh[t] = pack2(-bd, 1536.f);
  }
  asm volatile("{\n.reg .pred p, r;\nsetp.ne.b32 p, %0, 0;\nbarrier.red.or.pred r, 5, 512, p;\nselp.b32 %0, 1, 0, r;\n}" : "+r"(unsafe)::"memory");
  unsafe = __any_sync(~0u, unsafe);
  if (!unsafe && q == 1) { qa[0][4] = sh[0]; qa[0][5] = sh[1]; qa[1][4] = sh[2]; qa[1][5] = sh[3]; }
  put_q(qw + 16384, qa[1]);
  if (!unsafe) {
    attn_pass<true, 2>(qa[0], qw + 16384, op, z);
  } else {
    put_q(qw, qa[0]);
    fence_async();
    bar_sync(wg + 1, 128);
#pragma unroll 1
    for (int t = 0; t < 2; t++) {
      float m0, m1;
      attn_rowmax(qs + t * 16384, ks, bars, m0, m1);
      float h0 = bf_round(m0), h1 = bf_round(m1), i0 = bf_round(m0 - h0), i1 = bf_round(m1 - h1);
      get_q(qw + t * 16384, qa[0]);
      if (q == 1) { qa[0][4] = pack2(-h0, 0.f); qa[0][5] = pack2(-h1, 0.f); }
      if (q == 2) { qa[0][4] = pack2(-i0, -(m0 - h0 - i0)); qa[0][5] = pack2(-i1, -(m1 - h1 - i1)); }
      attn_pass<false, 1>(qa[0], 0, op + t * 64 * 288, z);
    }
  }
  TL(1, 3);
}

constexpr int KM_A = 9 * 8192, KM_BS = 9216;
constexpr int KM_SMEM = KM_A + 17 * KM_BS + 272;
struct MidMaps { CUtensorMap lo, lh, lg, sh, sg, sx1, sout; };
#define KM_MC 0
__device__ __forceinline__ void mid_rel(uint32_t b, uint32_t peer) { mb_arrive(b); if (KM_MC) mb_arrive_cl(b, peer); }

template <int WG>
__device__ __forceinline__ void mid_mma(float (&acc)[36], uint32_t par, uint32_t peer, bool rel) {
  const uint32_t sb = s2u(dsm), bars = sb + KM_A + 17 * KM_BS;
  const uint64_t da = mkdesc(sb, 16, 1024, 1), db = mkdesc(sb + KM_A, 1152, 128, 0);
  if (WG) {
#pragma unroll 1
    for (int ks = 1; ks < 9; ks++) mb_wait(bars + ks * 8, par);
    bar_sync(1, 256);
  }
#pragma unroll
  for (int ks = 0; ks < 9; ks++) {
    if (!WG && ks) mb_wait(bars + ks * 8, par);
    if (ks >= 6) mb_wait(bars + 72 + WG * 72 + ks * 8, par);
    if (!WG || ks == 0 || ks >= 6) wg_fence();
#pragma unroll
    for (int k = 0; k < 4; k++) wgmma_ss_n72_tb(acc, da + ks * 512 + k * 2, db + (WG && ks == 8 ? 0 : WG * 9 + ks) * 576 + k * 144, (ks | k) != 0);
    if (ks % 3 == 2) wg_commit();
    if (ks == 5 || ks == 8) {
      wg_wait<1>();
      if (!WG && ks == 5) asm volatile("bar.arrive 1, 256;" ::: "memory");
      if ((threadIdx.x & 127) == 0 && (rel || (!WG && ks == 5))) mid_rel(bars + 216 + (WG ? (ks == 5 ? 16 : 24) : (ks == 5 ? 0 : 8)), peer);
    }
  }
  wg_wait<0>();
  if (WG && threadIdx.x == 128 && rel) mid_rel(bars + 248, peer);
  reg_fence(acc);
}
__device__ __forceinline__ void put_stats(uint32_t a, int q, float s0, float q0, float s1, float q1) {
  s0 += __shfl_xor_sync(~0u, s0, 1); q0 += __shfl_xor_sync(~0u, q0, 1); s1 += __shfl_xor_sync(~0u, s1, 1); q1 += __shfl_xor_sync(~0u, q1, 1);
  s0 += __shfl_xor_sync(~0u, s0, 2); q0 += __shfl_xor_sync(~0u, q0, 2); s1 += __shfl_xor_sync(~0u, s1, 2); q1 += __shfl_xor_sync(~0u, q1, 2);
  if (q < 2) asm volatile("st.shared.v2.f32 [%0], {%1, %2};" ::"r"(a + q * 64), "f"(q ? s1 : s0), "f"(q ? q1 : q0) : "memory");
}

__global__ void __launch_bounds__(320, 1)
k3_mid(const __grid_constant__ MidMaps mp, const bf16* __restrict__ x) {
  const uint32_t sb = s2u(dsm), bars = sb + KM_A + 17 * KM_BS;
  const int rk = blockIdx.x & 1, tj = (blockIdx.x >> 1) & 3, ti = (blockIdx.x >> 3) * 2 + rk;
#define KM_ROT 1
  const int rot = KM_ROT ? (blockIdx.x >> 3) % 9 : 0;
  const int warp = threadIdx.x >> 5, lane = threadIdx.x & 31;
  if (threadIdx.x == 0) {
#pragma unroll
    for (int i = 0; i < 33; i++) mb_init(bars + i * 8, i < 27 ? 1 : 1 + KM_MC);
    fence_mb_init();
  }
  if (KM_MC) cluster_sync(); else __syncthreads();
  TR(threadIdx.x == 0, 20);
  pdl_launch();
  if (warp == 8) {
    if (lane == 0) {
#pragma unroll 1
      for (int r = 0; r < 4; r++) {
#pragma unroll 1
        for (int i = r ? 0 : 1; i < (r < 3 ? 18 : 1); i++) {
          const int t = r == 0 ? i - 1 : (int)((i < 9 ? 0xb524a418831ull >> (i * 5) : 0x839a0f039acull >> (i * 5 - 45)) & 31);
          if (r && i % 3 == 0) mb_wait(bars + 216 + (i / 3) * 8, (r - 1) & 1);
          if (r == 0 && i == 10) mb_wait(bars + 72 + 56, 0);
          TR(r < 2 && (i == 1 || i == 15), r * 10 + 8 + (i >> 3));
          const uint8_t* src = (const uint8_t*)g_wimg + ((r - (t == 17)) * 4 + tj) * (18 * KM_BS) + ((t >= 9 ? 9 : 0) + (t + rot) % 9) * KM_BS;
          mb_expect(bars + 72 + t * 8, KM_BS);
          if (!KM_MC) bulk_g2s(sb + KM_A + (t < 17 ? t : 0) * KM_BS, src, KM_BS, bars + 72 + t * 8);
          else if ((i & 1) == rk) bulk_g2s_mc(sb + KM_A + (t < 17 ? t : 0) * KM_BS, src, KM_BS, bars + 72 + t * 8, 3);
        }
      }
    }
  } else if (warp == 9) {
    pdl_wait();
#pragma unroll 1
    for (int ph = 0; ph < 3; ph++) {
      if (ph > 0) {
        const unsigned* p = ph == 1 ? &g_cm[ti] : &g_cm[32 + min(max(ti + (lane % 3) - 1, 0), 31)];
        int n = 0;
        while (!__all_sync(~0u, ld_acquire(p) >= 8u) && ++n < SPIN_MAX) {}
      }
      if (lane == 0) {
        TR(1, ph * 10 + 1);
        const CUtensorMap* m = ph == 0 ? &mp.lo : (ph == 1 ? &mp.lh : &mp.lg);
#pragma unroll 1
        for (int ks = 0; ks < 9; ks++) { mb_expect(bars + ks * 8, 8192); tma2d(sb + ks * 8192, m, ((ks + rot) % 9) * 64, ti * 64, bars + ks * 8); }
      }
      __syncwarp();
    }
  } else {
    const int wg = __shfl_sync(~0u, warp >> 2, 0), g = lane >> 2, q = lane & 3;
    const int lr = (warp & 3) * 16 + g, r0 = ti * 64 + lr, cb = tj * 144 + wg * 72;
    const uint32_t stg = wg ? sb : sb + KM_A + 6 * KM_BS, sw = stg + lr * 144 + q * 4, sst = stg + 2 * KM_BS;
    const bool el = (threadIdx.x & 127) == 0;
    uint32_t hp[18];
    {
      const uint32_t* p = (const uint32_t*)(x + (size_t)r0 * D_ + cb) + q;
#pragma unroll
      for (int c = 0; c < 9; c++) { hp[2 * c] = __ldg(p + c * 4); hp[2 * c + 1] = __ldg(p + 8 * 288 + c * 4); }
    }
    float acc[36];
    float2 cs[9], sa, sc;
    float mu0 = 0, mu1 = 0, ra = 0, rb = 0;
#pragma unroll 1
    for (int ph = 0; ph < 3; ph++) {
      const uint32_t par = ph & 1;
#pragma unroll 1
      for (int t = 0; t < 6; t++) mb_wait(bars + 72 + wg * 72 + t * 8, par);
      mb_wait(bars, par);
      if (ph == 1) {
#pragma unroll
        for (int c = 0; c < 9; c++) cs[c] = __ldcg((const float2*)(g_cs1 + cb + c * 8 + q * 2));
        sa = stat_ld(g_st_h, r0, q); sc = stat_ld(g_st_h, r0 + 8, q);
      }
      TR(el, ph * 10 + 2 + wg * 3);
      if (wg) mid_mma<1>(acc, par, rk ^ 1, ph < 2); else mid_mma<0>(acc, par, rk ^ 1, ph < 2);
      TR(el, ph * 10 + 3 + wg * 3);
      if (ph == 1) {
        float v0, v1;
        stat_fin(sa, mu0, v0); stat_fin(sc, mu1, v1);
        ra = rsqrtf(v0 + LN_EPS); rb = rsqrtf(v1 + LN_EPS);
        const float za = ra * rsqrtf(v0 * ra * ra + LN_EPS), zb = rb * rsqrtf(v1 * rb * rb + LN_EPS);
        const float ca0 = GELU_C0 * za, cb0 = GELU_C1 * za * za * za, ch0 = 0.5f * za;
        const float ca1 = GELU_C0 * zb, cb1 = GELU_C1 * zb * zb * zb, ch1 = 0.5f * zb;
#pragma unroll
        for (int c = 0; c < 9; c++) {
          sts32(sw + c * 16, pack2(gelu_s(fmaf(-mu0, cs[c].x, acc[c * 4]), ca0, cb0, ch0), gelu_s(fmaf(-mu0, cs[c].y, acc[c * 4 + 1]), ca0, cb0, ch0)));
          sts32(sw + 1152 + c * 16, pack2(gelu_s(fmaf(-mu1, cs[c].x, acc[c * 4 + 2]), ca1, cb1, ch1), gelu_s(fmaf(-mu1, cs[c].y, acc[c * 4 + 3]), ca1, cb1, ch1)));
        }
      } else {
        if (ph == 0) { ra = 1.f; rb = 1.f; }
        float s0 = 0, q0 = 0, s1 = 0, q1 = 0;
#pragma unroll
        for (int c = 0; c < 9; c++) {
          float a0 = blo(hp[2 * c]), a1 = bhi(hp[2 * c]), b0 = blo(hp[2 * c + 1]), b1 = bhi(hp[2 * c + 1]);
          uint32_t w0 = pack2(fmaf(a0 - mu0, ra, acc[c * 4]), fmaf(a1 - mu0, ra, acc[c * 4 + 1]));
          uint32_t w1 = pack2(fmaf(b0 - mu1, rb, acc[c * 4 + 2]), fmaf(b1 - mu1, rb, acc[c * 4 + 3]));
          sts32(sw + c * 16, w0); sts32(sw + 1152 + c * 16, w1);
          if (ph) { sts32(sw + KM_BS + c * 16, pack2(a0 + blo(w0), a1 + bhi(w0))); sts32(sw + KM_BS + 1152 + c * 16, pack2(b0 + blo(w1), b1 + bhi(w1))); }
          hp[2 * c] = w0; hp[2 * c + 1] = w1;
          s0 += blo(w0) + bhi(w0); q0 = fmaf(blo(w0), blo(w0), fmaf(bhi(w0), bhi(w0), q0));
          s1 += blo(w1) + bhi(w1); q1 = fmaf(blo(w1), blo(w1), fmaf(bhi(w1), bhi(w1), q1));
        }
        put_stats(sst + lr * 8, q, s0, q0, s1, q1);
      }
      fence_async();
      bar_sync(2 + wg, 128);
      if (el) {
        const int sh = tj == 0 ? 1 : (tj == 1 ? -1 : (tj == 2 ? 2 : -2));
        tma2d_st(ph == 0 ? &mp.sh : (ph == 1 ? &mp.sg : &mp.sx1), cb, ti * 64 + (ph == 1 ? sh + 2 : 0), stg);
        if (ph != 1) bulk_s2g((ph == 0 ? g_st_h : g_st_x1) + (tj * 2 + wg) * S_ + ti * 64, sst, 512);
        if (ph == 2) tma2d_st(&mp.sout, cb, ti * 64, stg + KM_BS);
        bulk_commit();
        if (ph < 2 && !wg) { bulk_wait_read<0>(); mid_rel(bars + 256, rk ^ 1); }
        if (ph < 2) { bulk_wait<0>(); red_relaxed(&g_cm[ph * 32 + ti]); }
        else bulk_wait_read<0>();
        TR(1, ph * 10 + 4 + wg * 3);
      }
      __syncwarp();
    }
  }
}

#define K6_ROT 0
constexpr int K6_PARK = 147456, K6_RING = 9 * 8192;
constexpr int K6_SMEM = K6_PARK + K6_RING + 2304 + 256;
struct RowC { float mu0, mu1, ca0, cb0, ch0, ca1, cb1, ch1; };

template <int EPI, bool DRAIN>
__device__ __forceinline__ void mlp_sub(float (&cur)[32], float (&prv)[32], uint32_t (&A)[144], uint32_t ring, uint32_t bars, uint32_t ph,
                                        const RowC& rc, const float* cs, uint32_t park, const CUtensorMap* mo, int ox, int oy, bool first) {
  const int lane = threadIdx.x & 31;
  uint32_t hp[4];
#pragma unroll
  for (int s = 0; s < 9; s++) {
    if (EPI == 0) {
      const int lr = lane & 15;
      mb_wait(bars + 160 + s * 8, 0);
#pragma unroll
      for (int k = 0; k < 4; k++)
        asm volatile("ldmatrix.sync.aligned.m8n8.x4.shared.b16 {%0,%1,%2,%3}, [%4];" : "=r"(A[s * 16 + k * 4]), "=r"(A[s * 16 + k * 4 + 1]), "=r"(A[s * 16 + k * 4 + 2]), "=r"(A[s * 16 + k * 4 + 3])
                     : "r"(park + s * 16384 + lr * 128 + (((k * 2 + (lane >> 4)) ^ (lr & 7)) << 4)) : "memory");
    }
    mb_wait(bars + s * 8, ph);
    uint64_t db = mkdesc(ring + s * 8192, 8192, 1024, 1);
    wg_fence();
#pragma unroll
    for (int k = 0; k < 4; k++) wgmma_rs_n64_tb(cur, A[s * 16 + k * 4], A[s * 16 + k * 4 + 1], A[s * 16 + k * 4 + 2], A[s * 16 + k * 4 + 3], db + k * 128, (s | k) != 0);
    wg_commit();
    if (EPI == 2 && s < 7) {
#pragma unroll
      for (int k = 0; k < 4; k++)
        asm volatile("ld.shared.v4.b32 {%0,%1,%2,%3}, [%4];" : "=r"(A[(s + 1) * 16 + k * 4]), "=r"(A[(s + 1) * 16 + k * 4 + 1]), "=r"(A[(s + 1) * 16 + k * 4 + 2]), "=r"(A[(s + 1) * 16 + k * 4 + 3])
                     : "r"(park + (s + 1) * 16384 + k * 512 + lane * 16) : "memory");
    }
    if (EPI == 3 && s == 1) { if (lane == 0) bulk_wait_read<1>(); __syncwarp(); }
    if (EPI != 0 && (EPI == 2 ? s < 8 : s >= 1)) {
      const int p = EPI == 2 ? s : s - 1;
      if (EPI == 1 || EPI == 2) {
        float2 c2 = *(const float2*)(cs + p * 8);
        uint32_t w0 = pack2(gelu_s(fmaf(-rc.mu0, c2.x, prv[p * 4]), rc.ca0, rc.cb0, rc.ch0), gelu_s(fmaf(-rc.mu0, c2.y, prv[p * 4 + 1]), rc.ca0, rc.cb0, rc.ch0));
        uint32_t w1 = pack2(gelu_s(fmaf(-rc.mu1, c2.x, prv[p * 4 + 2]), rc.ca1, rc.cb1, rc.ch1), gelu_s(fmaf(-rc.mu1, c2.y, prv[p * 4 + 3]), rc.ca1, rc.cb1, rc.ch1));
        if (EPI == 2) { A[128 + p * 2] = w0; A[128 + p * 2 + 1] = w1; }
        else {
          hp[(p & 1) * 2] = w0; hp[(p & 1) * 2 + 1] = w1;
          if (p & 1) asm volatile("st.shared.v4.b32 [%0], {%1,%2,%3,%4};" ::"r"(park + (p >> 1) * 512 + lane * 16), "r"(hp[0]), "r"(hp[1]), "r"(hp[2]), "r"(hp[3]) : "memory");
        }
      } else {
        const int g = lane >> 2, q = lane & 3;
        uint32_t a = park + g * 128 + ((p ^ g) << 4) + q * 4;
        asm volatile("st.shared.b32 [%0], %1;" ::"r"(a), "r"(pack2(prv[p * 4], prv[p * 4 + 1])) : "memory");
        asm volatile("st.shared.b32 [%0], %1;" ::"r"(a + 1024), "r"(pack2(prv[p * 4 + 2], prv[p * 4 + 3])) : "memory");
        if (p == 7) {
          fence_async();
          __syncwarp();
          if (lane == 0) { tma2d_red_add(mo, ox, oy, park); bulk_commit(); }
        }
      }
    }
    if (s > 0 || !first) {
      wg_wait<1>();
      if (s == 0) reg_fence(prv);
      if ((threadIdx.x & 127) == 0) mb_arrive(bars + 80 + ((s + 8) % 9) * 8);
    }
  }
  if (DRAIN) {
    wg_wait<0>();
    reg_fence(cur);
    if ((threadIdx.x & 127) == 0) mb_arrive(bars + 80 + 8 * 8);
  }
}

__global__ void __launch_bounds__(384, 1)
k6_mlp(const __grid_constant__ CUtensorMap mx, const __grid_constant__ CUtensorMap mw3, const __grid_constant__ CUtensorMap mw4, const __grid_constant__ CUtensorMap mo) {
  uint8_t* const sm = dsm;
  const uint32_t sb = s2u(sm), ring = sb + K6_PARK, bars = sb + K6_PARK + K6_RING + 2304;
  float* cs = (float*)(sm + K6_PARK + K6_RING);
  const int ti = blockIdx.x >> 3, tj = blockIdx.x & 7;
  TL(5, 0);
  const int warp = threadIdx.x >> 5, lane = threadIdx.x & 31;
  if (threadIdx.x == 0) {
    for (int s = 0; s < 9; s++) { mb_init(bars + s * 8, 1); mb_init(bars + 80 + s * 8, 2); mb_init(bars + 160 + s * 8, 1); }
    fence_mb_init();
  }
  __syncthreads();
  if (warp >= 8) {
    reg_dec<24>();
    if (warp == 8 && lane == 0) {
      const int rot = K6_ROT;
      for (int s = 0; s < 6; s++) { mb_expect(bars + s * 8, 8192); tma2d(ring + s * 8192, &mw3, tj * 576, (s + rot) % 9 * 64, bars + s * 8); }
      pdl_wait();
      for (int s = 0; s < 9; s++) {
        mb_expect(bars + 160 + s * 8, 16384); tma2d(sb + s * 16384, &mx, (s + rot) % 9 * 64, ti * 128, bars + 160 + s * 8);
        if (s >= 6) { mb_expect(bars + s * 8, 8192); tma2d(ring + s * 8192, &mw3, tj * 576, (s + rot) % 9 * 64, bars + s * 8); }
      }
      for (int T = 1; T < 18; T++) {
        for (int s = 0; s < 9; s++) {
          mb_wait(bars + 80 + s * 8, (T & 1) ^ 1);
          mb_expect(bars + s * 8, 8192);
          if (T < 9) tma2d(ring + s * 8192, &mw3, tj * 576 + T * 64, (s + rot) % 9 * 64, bars + s * 8);
          else tma2d(ring + s * 8192, &mw4, ((T - 9 + tj) % 9) * 64, tj * 576 + s * 64, bars + s * 8);
        }
      }
    }
  } else {
    reg_inc<240>();
    const int g = lane >> 2, q = lane & 3;
    const int r0 = ti * 128 + warp * 16;
    pdl_wait();
    TL(5, 1);
    const float c0 = __ldcg(g_cs3 + tj * 576 + threadIdx.x), c1 = __ldcg(g_cs3 + tj * 576 + 256 + threadIdx.x), c2 = __ldcg(g_cs3 + tj * 576 + 512 + (threadIdx.x & 63));
    const float2 sa = stat_ld(g_st_x1, r0 + g, q), sc = stat_ld(g_st_x1, r0 + g + 8, q);
    RowC rc;
    uint32_t A[144];
    const uint32_t park = sb + warp * 2048;
    float acc0[32], acc1[32];
    const float* csq = cs + q * 2;
    mlp_sub<0, true>(acc0, acc1, A, ring, bars, 0, rc, csq, park, &mo, 0, 0, true);
    TL(5, 2);
    {
      cs[threadIdx.x] = c0; cs[256 + threadIdx.x] = c1; cs[512 + (threadIdx.x & 63)] = c2;
      float v0, v1;
      stat_fin(sa, rc.mu0, v0); stat_fin(sc, rc.mu1, v1);
      float ra = rsqrtf(v0 + LN_EPS), rb = rsqrtf(v1 + LN_EPS);
      rc.ca0 = GELU_C0 * ra; rc.cb0 = GELU_C1 * ra * ra * ra; rc.ch0 = 0.5f * ra;
      rc.ca1 = GELU_C0 * rb; rc.cb1 = GELU_C1 * rb * rb * rb; rc.ch1 = 0.5f * rb;
    }
    bar_sync(1, 256);
#pragma unroll 1
    for (int t = 1; t < 9; t += 2) {
      mlp_sub<1, false>(acc1, acc0, A, ring, bars, 1, rc, csq + (t - 1) * 64, park + (t - 1) * 16384, &mo, 0, 0, true);
      mlp_sub<1, true>(acc0, acc1, A, ring, bars, 0, rc, csq + t * 64, park + t * 16384, &mo, 0, 0, false);
    }
#pragma unroll
    for (int k = 0; k < 4; k++)
      asm volatile("ld.shared.v4.b32 {%0,%1,%2,%3}, [%4];" : "=r"(A[k * 4]), "=r"(A[k * 4 + 1]), "=r"(A[k * 4 + 2]), "=r"(A[k * 4 + 3]) : "r"(park + k * 512 + lane * 16) : "memory");
    TL(5, 3);
    mlp_sub<2, true>(acc1, acc0, A, ring, bars, 1, rc, csq + 8 * 64, park, &mo, 0, 0, true);
    __syncwarp();
#pragma unroll 1
    for (int t = 1; t < 9; t += 2) {
      mlp_sub<3, false>(acc0, acc1, A, ring, bars, 0, rc, csq, park, &mo, ((t - 1 + tj) % 9) * 64, r0, true);
      mlp_sub<3, true>(acc1, acc0, A, ring, bars, 1, rc, csq, park + 16384, &mo, ((t + tj) % 9) * 64, r0, false);
    }
    TL(5, 4);
    const uint32_t stg = park + 32768;
#pragma unroll
    for (int p = 0; p < 8; p++) {
      uint32_t a = stg + g * 128 + ((p ^ g) << 4) + q * 4;
      asm volatile("st.shared.b32 [%0], %1;" ::"r"(a), "r"(pack2(acc1[p * 4], acc1[p * 4 + 1])) : "memory");
      asm volatile("st.shared.b32 [%0], %1;" ::"r"(a + 1024), "r"(pack2(acc1[p * 4 + 2], acc1[p * 4 + 3])) : "memory");
    }
    fence_async();
    __syncwarp();
    if (lane == 0) { tma2d_red_add(&mo, ((8 + tj) % 9) * 64, r0, stg); bulk_commit(); bulk_wait_read<0>(); }
    TL(5, 5);
  }
}

typedef CUresult (*EncFn)(CUtensorMap*, CUtensorMapDataType, cuuint32_t, void*, const cuuint64_t*, const cuuint64_t*, const cuuint32_t*, const cuuint32_t*,
                          CUtensorMapInterleave, CUtensorMapSwizzle, CUtensorMapL2promotion, CUtensorMapFloatOOBfill);
static CUtensorMap mk_map(EncFn enc, const void* p, int cols, int rows, int bx, int by, CUtensorMapSwizzle sw = CU_TENSOR_MAP_SWIZZLE_128B) {
  CUtensorMap m;
  cuuint64_t gd[2] = {(cuuint64_t)cols, (cuuint64_t)rows}, gs[1] = {(cuuint64_t)cols * 2};
  cuuint32_t b[2] = {(cuuint32_t)bx, (cuuint32_t)by}, es[2] = {1, 1};
  enc(&m, CU_TENSOR_MAP_DATA_TYPE_BFLOAT16, 2, (void*)p, gd, gs, b, es, CU_TENSOR_MAP_INTERLEAVE_NONE, sw, CU_TENSOR_MAP_L2_PROMOTION_L2_128B, CU_TENSOR_MAP_FLOAT_OOB_FILL_NONE);
  return m;
}
template <typename... KA, typename... A>
static void launch(void (*k)(KA...), int grid, int block, int smem, bool pdl, int cluster, A... args) {
  cudaLaunchConfig_t cfg = {};
  cfg.gridDim = dim3(grid); cfg.blockDim = dim3(block); cfg.dynamicSmemBytes = smem; cfg.stream = cudaStreamPerThread;
  cudaLaunchAttribute at[2];
  int n = 0;
  if (pdl) { at[n].id = cudaLaunchAttributeProgrammaticStreamSerialization; at[n].val.programmaticStreamSerializationAllowed = 1; n++; }
  if (cluster > 1) { at[n].id = cudaLaunchAttributeClusterDimension; at[n].val.clusterDim.x = cluster; at[n].val.clusterDim.y = 1; at[n].val.clusterDim.z = 1; n++; }
  cfg.attrs = at; cfg.numAttrs = n;
  cudaLaunchKernelEx(&cfg, k, args...);
}

extern "C" void kernel_launch(void* const* d_in, const int* in_sizes, int n_in, void* d_out, int out_size) {
  const bf16* x = (const bf16*)d_in[0];
  const bf16* wqkv = (const bf16*)d_in[1];
  const bf16* wo = (const bf16*)d_in[2];
  const bf16* w1 = (const bf16*)d_in[4];
  const bf16* w2 = (const bf16*)d_in[5];
  const bf16* w3 = (const bf16*)d_in[6];
  const bf16* w4 = (const bf16*)d_in[7];
  bf16* out = (bf16*)d_out;
  void* fn = nullptr;
  cudaDriverEntryPointQueryResult qr;
  cudaGetDriverEntryPoint("cuTensorMapEncodeTiled", &fn, cudaEnableDefault, &qr);
  EncFn enc = (EncFn)fn;
  void *po, *ph, *pg, *px1;
  cudaGetSymbolAddress(&po, g_o); cudaGetSymbolAddress(&ph, g_h); cudaGetSymbolAddress(&pg, g_gs); cudaGetSymbolAddress(&px1, g_x1);
  CUtensorMap m_x = mk_map(enc, x, D_, S_, 64, 128);
  CUtensorMap m_wq[2];
  for (int i = 0; i < 2; i++) {
    cuuint64_t gd[3] = {(cuuint64_t)(i ? 432 : 224), 4, D_}, gs[2] = {864, 3456};
    cuuint32_t b[3] = {64, 1, 64}, es[3] = {1, 1, 1};
    enc(&m_wq[i], CU_TENSOR_MAP_DATA_TYPE_BFLOAT16, 3, (void*)wqkv, gd, gs, b, es, CU_TENSOR_MAP_INTERLEAVE_NONE, CU_TENSOR_MAP_SWIZZLE_128B, CU_TENSOR_MAP_L2_PROMOTION_L2_128B, CU_TENSOR_MAP_FLOAT_OOB_FILL_NONE);
  }
  CUtensorMap m_x1 = mk_map(enc, px1, D_, S_, 64, 128);
  MidMaps mm;
  mm.lo = mk_map(enc, po, D_, S_, 64, 64); mm.lh = mk_map(enc, ph, D_, S_, 64, 64); mm.lg = mk_map(enc, (bf16*)pg + 2 * D_, D_, S_, 64, 64);
  mm.sh = mk_map(enc, ph, D_, S_, 72, 64, CU_TENSOR_MAP_SWIZZLE_NONE); mm.sg = mk_map(enc, pg, D_, S_ + 4, 72, 64, CU_TENSOR_MAP_SWIZZLE_NONE);
  mm.sx1 = mk_map(enc, px1, D_, S_, 72, 64, CU_TENSOR_MAP_SWIZZLE_NONE); mm.sout = mk_map(enc, out, D_, S_, 72, 64, CU_TENSOR_MAP_SWIZZLE_NONE);
  CUtensorMap m_w3 = mk_map(enc, w3, F_, D_, 64, 64), m_w4 = mk_map(enc, w4, D_, F_, 64, 64), m_out = mk_map(enc, out, D_, S_, 64, 16);
  cudaFuncSetAttribute(k1_qkv, cudaFuncAttributeMaxDynamicSharedMemorySize, K1_SMEM);
  cudaFuncSetAttribute(k2_attn, cudaFuncAttributeMaxDynamicSharedMemorySize, K2_SMEM);
  cudaFuncSetAttribute(k3_mid, cudaFuncAttributeMaxDynamicSharedMemorySize, KM_SMEM);
  cudaFuncSetAttribute(k6_mlp, cudaFuncAttributeMaxDynamicSharedMemorySize, K6_SMEM);
  const bool P = true;
  launch(k1_qkv, 128, 384, K1_SMEM, false, 1, m_x, m_wq[0], m_wq[1], x, wqkv, wo, w1, w2);
  launch(k2_attn, 132, 512, K2_SMEM, P, 1, w1, w3, w4, make_uint4(0, 0, 0, 0));
  launch(k3_mid, 128, 320, KM_SMEM, P, 1 + KM_MC, mm, x);
  launch(k6_mlp, 128, 384, K6_SMEM, P, 1, m_x1, m_w3, m_w4, m_out);
}
```
